```python
import torch

def _softmax(x, axis=-1):
    return torch.softmax(x, dim=axis)
def _gelu(x):
    return torch.nn.functional.gelu(x, approximate="tanh")
def _silu(x):
    return torch.nn.functional.silu(x)
def _sigmoid(x):
    return torch.sigmoid(x)
def _layernorm(x, axis=-1, eps=1e-5):
    m = x.mean(dim=axis, keepdim=True)
    v = x.var(dim=axis, keepdim=True, unbiased=False)
    return (x - m) / torch.sqrt(v + eps)
def _scatter_add(tgt, idx, src, axis=0):
    return tgt.clone().index_add_(axis, idx, src)
def _segment_sum(src, seg, n):
    out = torch.zeros((n,) + src.shape[1:], dtype=src.dtype)
    return out.index_add_(0, seg, src)
def _pad(x, pw):
    flat = tuple(v for pair in reversed(pw) for v in pair)
    return torch.nn.functional.pad(x, flat)

kernel_name = 'sequential_preLN__softmax_full_mha__geglu_ffn__prompt'

def setup_inputs():

    _w = (lambda a: (lambda t: t.to(torch.bfloat16) if t.is_floating_point() else t)(torch.as_tensor(a)))
    def _A_setup():
        B, S, D = 1, 2048, 512
        return {
            "x": _w((lambda *s: torch.randn(*s, dtype=torch.bfloat16) * 0.05)(B, S, D)),
            "wqkv": _w((lambda *s: torch.randn(*s, dtype=torch.bfloat16) * 0.05)(D, 3 * D)),
            "wo": _w((lambda *s: torch.randn(*s, dtype=torch.bfloat16) * 0.05)(D, D)),
        }
    _A_in = _A_setup()

    def _B_setup():
        B, S, D, F = 1, 2048, 512, 1792
        return {
            "x": _w((lambda *s: torch.randn(*s, dtype=torch.bfloat16) * 0.05)(B, S, D)),
            "w_gate": _w((lambda *s: torch.randn(*s, dtype=torch.bfloat16) * 0.05)(D, F)),
            "w_up": _w((lambda *s: torch.randn(*s, dtype=torch.bfloat16) * 0.05)(D, F)),
            "w_down": _w((lambda *s: torch.randn(*s, dtype=torch.bfloat16) * 0.05)(F, D)),
        }
    _B_in = _B_setup()

    return {
        "A_x": _A_in["x"],
        "A_wqkv": _A_in["wqkv"],
        "A_wo": _A_in["wo"],
        "B_x": _B_in["x"],
        "B_w_gate": _B_in["w_gate"],
        "B_w_up": _B_in["w_up"],
        "B_w_down": _B_in["w_down"],
    }

def reference(A_x, A_wqkv, A_wo, B_x, B_w_gate, B_w_up, B_w_down):
    def _A_ref(x, wqkv, wo):
        B, S, D = x.shape
        H = 32; Dh = D // H
        qkv = (lambda x, *d: x.permute(*d))((x @ wqkv).reshape(B, S, 3, H, Dh), 2, 0, 3, 1, 4)
        q, k, v = qkv[0], qkv[1], qkv[2]
        scale = Dh ** -0.5
        scores = torch.einsum("bhqd,bhkd->bhqk", q, k) * scale
        p = _softmax(scores, axis=-1)
        o = torch.einsum("bhqk,bhkd->bhqd", p, v)
        return (lambda x, *d: x.permute(*d))(o, 0, 2, 1, 3).reshape(B, S, D) @ wo

    def _B_ref(x, w_gate, w_up, w_down):
        return (_gelu(x @ w_gate) * (x @ w_up)) @ w_down

    x = A_x
    h = x + _A_ref(_layernorm(x, axis=-1), A_wqkv, A_wo)
    h2 = h + _B_ref(_layernorm(h, axis=-1), B_w_gate, B_w_up, B_w_down)
    return h2
```

```cpp
#include <cuda_runtime.h>
#include <cuda_bf16.h>
#include <cuda.h>
#include <stdint.h>

namespace {

constexpr int S_ = 2048, D_ = 512, H_ = 32, F_ = 1792;
constexpr float LN_EPS = 1e-5f;
constexpr float QSCALE = 0.25f * 1.4426950408889634f;

__device__ __align__(1024) __nv_bfloat16 g_qkv[3 * H_ * 2 * S_ * 8];
__device__ __align__(16) float g_nrm[3 * H_ * 128];
__device__ __align__(1024) __nv_bfloat16 g_o[S_ * D_];
__device__ __align__(1024) __nv_bfloat16 g_h[S_ * D_];
__device__ __align__(1024) __nv_bfloat16 g_act[S_ * F_];
__device__ __align__(16) float2 g_stats[S_ * 8];
__device__ __align__(16) float g_cs[2 * F_];
__device__ __align__(16) float2 g_rs[S_];
__device__ __align__(16) float g_csp[16 * 3 * D_];
__device__ unsigned int g_cnt[32];

#define TS(kern, slot, cond)
#define TC(kern, slot, cond)
__device__ __forceinline__ uint32_t smem_u32(const void* p) { return (uint32_t)__cvta_generic_to_shared(p); }
__device__ __forceinline__ void mbar_init(uint32_t bar, int cnt) {
    asm volatile("mbarrier.init.shared::cta.b64 [%0], %1;" ::"r"(bar), "r"(cnt));
}
__device__ __forceinline__ void mbar_expect_tx(uint32_t bar, uint32_t bytes) {
    asm volatile("mbarrier.arrive.expect_tx.shared::cta.b64 _, [%0], %1;" ::"r"(bar), "r"(bytes) : "memory");
}
__device__ __forceinline__ void mbar_arrive(uint32_t bar) {
    asm volatile("mbarrier.arrive.shared::cta.b64 _, [%0];" ::"r"(bar) : "memory");
}
__device__ __forceinline__ void mbar_wait(uint32_t bar, uint32_t parity) {
    asm volatile(
        "{\n.reg .pred p;\n.reg .u32 c;\nmov.u32 c, 0;\n"
        "LAB_WAIT:\n"
        "mbarrier.try_wait.parity.shared::cta.b64 p, [%0], %1;\n"
        "@p bra LAB_DONE;\n"
        "add.u32 c, c, 1;\nsetp.lt.u32 p, c, 4194304;\n"
        "@p bra LAB_WAIT;\n"
        "LAB_DONE:\n}\n" ::"r"(bar), "r"(parity) : "memory");
}
__device__ __forceinline__ void fence_barrier_init() { asm volatile("fence.mbarrier_init.release.cluster;" ::: "memory"); }
__device__ __forceinline__ void fence_proxy_async() { asm volatile("fence.proxy.async.shared::cta;" ::: "memory"); }
__device__ __forceinline__ void tma_load_2d(uint32_t dst, const CUtensorMap* tm, int c0, int c1, uint32_t bar) {
    asm volatile("cp.async.bulk.tensor.2d.shared::cluster.global.mbarrier::complete_tx::bytes [%0], [%1, {%3, %4}], [%2];"
                 ::"r"(dst), "l"(tm), "r"(bar), "r"(c0), "r"(c1) : "memory");
}
__device__ __forceinline__ void tma_load_3d(uint32_t dst, const CUtensorMap* tm, int c0, int c1, int c2, uint32_t bar) {
    asm volatile("cp.async.bulk.tensor.3d.shared::cluster.global.mbarrier::complete_tx::bytes [%0], [%1, {%3, %4, %5}], [%2];"
                 ::"r"(dst), "l"(tm), "r"(bar), "r"(c0), "r"(c1), "r"(c2) : "memory");
}
__device__ __forceinline__ void bulk_load(uint32_t dst, const void* src, uint32_t bytes, uint32_t bar) {
    asm volatile("cp.async.bulk.shared::cluster.global.mbarrier::complete_tx::bytes [%0], [%1], %2, [%3];"
                 ::"r"(dst), "l"(src), "r"(bytes), "r"(bar) : "memory");
}
__device__ __forceinline__ void bulk_prefetch_l2(const void* src, uint32_t bytes) {
    asm volatile("cp.async.bulk.prefetch.L2.global [%0], %1;" ::"l"(src), "r"(bytes) : "memory");
}
__device__ __forceinline__ void pdl_wait() { asm volatile("griddepcontrol.wait;" ::: "memory"); }
__device__ __forceinline__ void pdl_launch() { asm volatile("griddepcontrol.launch_dependents;" ::: "memory"); }
__device__ __forceinline__ void wg_fence() { asm volatile("wgmma.fence.sync.aligned;" ::: "memory"); }
__device__ __forceinline__ void wg_commit() { asm volatile("wgmma.commit_group.sync.aligned;" ::: "memory"); }
template <int N> __device__ __forceinline__ void wg_wait() { asm volatile("wgmma.wait_group.sync.aligned %0;" ::"n"(N) : "memory"); }
template <int N> __device__ __forceinline__ void fence_regs(float (&d)[N]) {
#pragma unroll
    for (int i = 0; i < N; i++) asm volatile("" : "+f"(d[i])::"memory");
}
__device__ __forceinline__ void named_bar_sync(int id, int n) { asm volatile("bar.sync %0, %1;" ::"r"(id), "r"(n) : "memory"); }
__device__ __forceinline__ void named_bar_arrive(int id, int n) { asm volatile("bar.arrive %0, %1;" ::"r"(id), "r"(n) : "memory"); }
__device__ __forceinline__ uint4 lds128(uint32_t a) {
    uint4 v;
    asm volatile("ld.shared.v4.u32 {%0,%1,%2,%3}, [%4];" : "=r"(v.x), "=r"(v.y), "=r"(v.z), "=r"(v.w) : "r"(a));
    return v;
}
__device__ __forceinline__ void sts128(uint32_t a, uint32_t x, uint32_t y, uint32_t z, uint32_t w) {
    asm volatile("st.shared.v4.u32 [%0], {%1,%2,%3,%4};" ::"r"(a), "r"(x), "r"(y), "r"(z), "r"(w) : "memory");
}
__device__ __forceinline__ void stmatrix_x4(uint32_t a, uint32_t r0, uint32_t r1, uint32_t r2, uint32_t r3) {
    asm volatile("stmatrix.sync.aligned.m8n8.x4.shared.b16 [%0], {%1,%2,%3,%4};" ::"r"(a), "r"(r0), "r"(r1), "r"(r2), "r"(r3) : "memory");
}
__device__ __forceinline__ void bulk_store(void* dst, uint32_t src, uint32_t bytes) {
    asm volatile("cp.async.bulk.global.shared::cta.bulk_group [%0], [%1], %2;" ::"l"(dst), "r"(src), "r"(bytes) : "memory");
}
__device__ __forceinline__ void tma_store_2d(const CUtensorMap* tm, uint32_t src, int c0, int c1) {
    asm volatile("cp.async.bulk.tensor.2d.global.shared::cta.bulk_group [%0, {%2, %3}], [%1];" ::"l"(tm), "r"(src), "r"(c0), "r"(c1) : "memory");
}
__device__ __forceinline__ void tma_store_3d(const CUtensorMap* tm, uint32_t src, int c0, int c1, int c2) {
    asm volatile("cp.async.bulk.tensor.3d.global.shared::cta.bulk_group [%0, {%2, %3, %4}], [%1];" ::"l"(tm), "r"(src), "r"(c0), "r"(c1), "r"(c2) : "memory");
}
__device__ __forceinline__ void bulk_commit() { asm volatile("cp.async.bulk.commit_group;" ::: "memory"); }
__device__ __forceinline__ void bulk_wait_all() { asm volatile("cp.async.bulk.wait_group 0;" ::: "memory"); }
__device__ __forceinline__ void bulk_wait_read() { asm volatile("cp.async.bulk.wait_group.read 0;" ::: "memory"); }
__device__ __forceinline__ float bf_lo(uint32_t u) { return __uint_as_float(u << 16); }
__device__ __forceinline__ float bf_hi(uint32_t u) { return __uint_as_float(u & 0xFFFF0000u); }
__device__ __forceinline__ uint32_t pack_bf16(float lo, float hi) {
    uint32_t r;
    asm("cvt.rn.bf16x2.f32 %0, %1, %2;" : "=r"(r) : "f"(hi), "f"(lo));
    return r;
}
__device__ __forceinline__ float rbf(float x) { return __bfloat162float(__float2bfloat16_rn(x)); }
__device__ __forceinline__ float2 ln_consts(float mean, float var) {
    float sd, r;
    asm("sqrt.approx.f32 %0, %1;" : "=f"(sd) : "f"(rbf(rbf(var) + LN_EPS)));
    asm("rcp.approx.f32 %0, %1;" : "=f"(r) : "f"(rbf(sd)));
    return make_float2(r, rbf(mean));
}
__device__ __forceinline__ float ex2(float x) {
    float y;
    asm("ex2.approx.ftz.f32 %0, %1;" : "=f"(y) : "f"(x));
    return y;
}
__device__ __forceinline__ float tanh_fast(float x) {
    float y;
    asm("tanh.approx.f32 %0, %1;" : "=f"(y) : "f"(x));
    return y;
}
__device__ __forceinline__ uint64_t make_desc(uint32_t addr, uint32_t lbo, uint32_t sbo, uint32_t layout) {
    return (uint64_t)((addr & 0x3FFFF) >> 4) | ((uint64_t)(lbo >> 4) << 16) | ((uint64_t)(sbo >> 4) << 32) | ((uint64_t)layout << 62);
}

__device__ __forceinline__ void wgmma_ss_n64(float (&d)[32], uint64_t da, uint64_t db, int sd) {
    asm volatile("{\n.reg .pred p;\nsetp.ne.b32 p, %34, 0;\n"
        "wgmma.mma_async.sync.aligned.m64n64k16.f32.bf16.bf16 {%0, %1, %2, %3, %4, %5, %6, %7, %8, %9, %10, %11, %12, %13, %14, %15, %16, %17, %18, %19, %20, %21, %22, %23, %24, %25, %26, %27, %28, %29, %30, %31}, %32, %33, p, 1, 1, 0, 1;\n}\n"
        : "+f"(d[0]), "+f"(d[1]), "+f"(d[2]), "+f"(d[3]), "+f"(d[4]), "+f"(d[5]), "+f"(d[6]), "+f"(d[7]), "+f"(d[8]), "+f"(d[9]), "+f"(d[10]), "+f"(d[11]), "+f"(d[12]), "+f"(d[13]), "+f"(d[14]), "+f"(d[15]), "+f"(d[16]), "+f"(d[17]), "+f"(d[18]), "+f"(d[19]), "+f"(d[20]), "+f"(d[21]), "+f"(d[22]), "+f"(d[23]), "+f"(d[24]), "+f"(d[25]), "+f"(d[26]), "+f"(d[27]), "+f"(d[28]), "+f"(d[29]), "+f"(d[30]), "+f"(d[31])
        : "l"(da), "l"(db), "r"(sd));
}
__device__ __forceinline__ void wgmma_ss_n128(float (&d)[64], uint64_t da, uint64_t db, int sd) {
    asm volatile("{\n.reg .pred p;\nsetp.ne.b32 p, %66, 0;\n"
        "wgmma.mma_async.sync.aligned.m64n128k16.f32.bf16.bf16 {%0, %1, %2, %3, %4, %5, %6, %7, %8, %9, %10, %11, %12, %13, %14, %15, %16, %17, %18, %19, %20, %21, %22, %23, %24, %25, %26, %27, %28, %29, %30, %31, %32, %33, %34, %35, %36, %37, %38, %39, %40, %41, %42, %43, %44, %45, %46, %47, %48, %49, %50, %51, %52, %53, %54, %55, %56, %57, %58, %59, %60, %61, %62, %63}, %64, %65, p, 1, 1, 0, 1;\n}\n"
        : "+f"(d[0]), "+f"(d[1]), "+f"(d[2]), "+f"(d[3]), "+f"(d[4]), "+f"(d[5]), "+f"(d[6]), "+f"(d[7]), "+f"(d[8]), "+f"(d[9]), "+f"(d[10]), "+f"(d[11]), "+f"(d[12]), "+f"(d[13]), "+f"(d[14]), "+f"(d[15]), "+f"(d[16]), "+f"(d[17]), "+f"(d[18]), "+f"(d[19]), "+f"(d[20]), "+f"(d[21]), "+f"(d[22]), "+f"(d[23]), "+f"(d[24]), "+f"(d[25]), "+f"(d[26]), "+f"(d[27]), "+f"(d[28]), "+f"(d[29]), "+f"(d[30]), "+f"(d[31]), "+f"(d[32]), "+f"(d[33]), "+f"(d[34]), "+f"(d[35]), "+f"(d[36]), "+f"(d[37]), "+f"(d[38]), "+f"(d[39]), "+f"(d[40]), "+f"(d[41]), "+f"(d[42]), "+f"(d[43]), "+f"(d[44]), "+f"(d[45]), "+f"(d[46]), "+f"(d[47]), "+f"(d[48]), "+f"(d[49]), "+f"(d[50]), "+f"(d[51]), "+f"(d[52]), "+f"(d[53]), "+f"(d[54]), "+f"(d[55]), "+f"(d[56]), "+f"(d[57]), "+f"(d[58]), "+f"(d[59]), "+f"(d[60]), "+f"(d[61]), "+f"(d[62]), "+f"(d[63])
        : "l"(da), "l"(db), "r"(sd));
}
__device__ __forceinline__ void wgmma_ss_n192(float (&d)[96], uint64_t da, uint64_t db, int sd) {
    asm volatile("{\n.reg .pred p;\nsetp.ne.b32 p, %98, 0;\n"
        "wgmma.mma_async.sync.aligned.m64n192k16.f32.bf16.bf16 {%0, %1, %2, %3, %4, %5, %6, %7, %8, %9, %10, %11, %12, %13, %14, %15, %16, %17, %18, %19, %20, %21, %22, %23, %24, %25, %26, %27, %28, %29, %30, %31, %32, %33, %34, %35, %36, %37, %38, %39, %40, %41, %42, %43, %44, %45, %46, %47, %48, %49, %50, %51, %52, %53, %54, %55, %56, %57, %58, %59, %60, %61, %62, %63, %64, %65, %66, %67, %68, %69, %70, %71, %72, %73, %74, %75, %76, %77, %78, %79, %80, %81, %82, %83, %84, %85, %86, %87, %88, %89, %90, %91, %92, %93, %94, %95}, %96, %97, p, 1, 1, 0, 1;\n}\n"
        : "+f"(d[0]), "+f"(d[1]), "+f"(d[2]), "+f"(d[3]), "+f"(d[4]), "+f"(d[5]), "+f"(d[6]), "+f"(d[7]), "+f"(d[8]), "+f"(d[9]), "+f"(d[10]), "+f"(d[11]), "+f"(d[12]), "+f"(d[13]), "+f"(d[14]), "+f"(d[15]), "+f"(d[16]), "+f"(d[17]), "+f"(d[18]), "+f"(d[19]), "+f"(d[20]), "+f"(d[21]), "+f"(d[22]), "+f"(d[23]), "+f"(d[24]), "+f"(d[25]), "+f"(d[26]), "+f"(d[27]), "+f"(d[28]), "+f"(d[29]), "+f"(d[30]), "+f"(d[31]), "+f"(d[32]), "+f"(d[33]), "+f"(d[34]), "+f"(d[35]), "+f"(d[36]), "+f"(d[37]), "+f"(d[38]), "+f"(d[39]), "+f"(d[40]), "+f"(d[41]), "+f"(d[42]), "+f"(d[43]), "+f"(d[44]), "+f"(d[45]), "+f"(d[46]), "+f"(d[47]), "+f"(d[48]), "+f"(d[49]), "+f"(d[50]), "+f"(d[51]), "+f"(d[52]), "+f"(d[53]), "+f"(d[54]), "+f"(d[55]), "+f"(d[56]), "+f"(d[57]), "+f"(d[58]), "+f"(d[59]), "+f"(d[60]), "+f"(d[61]), "+f"(d[62]), "+f"(d[63]), "+f"(d[64]), "+f"(d[65]), "+f"(d[66]), "+f"(d[67]), "+f"(d[68]), "+f"(d[69]), "+f"(d[70]), "+f"(d[71]), "+f"(d[72]), "+f"(d[73]), "+f"(d[74]), "+f"(d[75]), "+f"(d[76]), "+f"(d[77]), "+f"(d[78]), "+f"(d[79]), "+f"(d[80]), "+f"(d[81]), "+f"(d[82]), "+f"(d[83]), "+f"(d[84]), "+f"(d[85]), "+f"(d[86]), "+f"(d[87]), "+f"(d[88]), "+f"(d[89]), "+f"(d[90]), "+f"(d[91]), "+f"(d[92]), "+f"(d[93]), "+f"(d[94]), "+f"(d[95])
        : "l"(da), "l"(db), "r"(sd));
}
__device__ __forceinline__ void wgmma_rs_n128_zero(float (&d)[64], uint32_t a0, uint32_t a1, uint32_t a2, uint32_t a3, uint64_t db) {
    asm volatile("{\n.reg .pred p;\nsetp.ne.b32 p, 0, 0;\n"
        "wgmma.mma_async.sync.aligned.m64n128k16.f32.bf16.bf16 {%0, %1, %2, %3, %4, %5, %6, %7, %8, %9, %10, %11, %12, %13, %14, %15, %16, %17, %18, %19, %20, %21, %22, %23, %24, %25, %26, %27, %28, %29, %30, %31, %32, %33, %34, %35, %36, %37, %38, %39, %40, %41, %42, %43, %44, %45, %46, %47, %48, %49, %50, %51, %52, %53, %54, %55, %56, %57, %58, %59, %60, %61, %62, %63}, {%64, %65, %66, %67}, %68, p, 1, 1, 0;\n}\n"
        : "=f"(d[0]), "=f"(d[1]), "=f"(d[2]), "=f"(d[3]), "=f"(d[4]), "=f"(d[5]), "=f"(d[6]), "=f"(d[7]), "=f"(d[8]), "=f"(d[9]), "=f"(d[10]), "=f"(d[11]), "=f"(d[12]), "=f"(d[13]), "=f"(d[14]), "=f"(d[15]), "=f"(d[16]), "=f"(d[17]), "=f"(d[18]), "=f"(d[19]), "=f"(d[20]), "=f"(d[21]), "=f"(d[22]), "=f"(d[23]), "=f"(d[24]), "=f"(d[25]), "=f"(d[26]), "=f"(d[27]), "=f"(d[28]), "=f"(d[29]), "=f"(d[30]), "=f"(d[31]), "=f"(d[32]), "=f"(d[33]), "=f"(d[34]), "=f"(d[35]), "=f"(d[36]), "=f"(d[37]), "=f"(d[38]), "=f"(d[39]), "=f"(d[40]), "=f"(d[41]), "=f"(d[42]), "=f"(d[43]), "=f"(d[44]), "=f"(d[45]), "=f"(d[46]), "=f"(d[47]), "=f"(d[48]), "=f"(d[49]), "=f"(d[50]), "=f"(d[51]), "=f"(d[52]), "=f"(d[53]), "=f"(d[54]), "=f"(d[55]), "=f"(d[56]), "=f"(d[57]), "=f"(d[58]), "=f"(d[59]), "=f"(d[60]), "=f"(d[61]), "=f"(d[62]), "=f"(d[63])
        : "r"(a0), "r"(a1), "r"(a2), "r"(a3), "l"(db));
}
__device__ __forceinline__ void wgmma_rs_n24_acc(float (&d)[12], uint32_t a0, uint32_t a1, uint32_t a2, uint32_t a3, uint64_t db) {
    asm volatile("{\n.reg .pred p;\nsetp.ne.b32 p, 1, 0;\n"
        "wgmma.mma_async.sync.aligned.m64n24k16.f32.bf16.bf16 {%0, %1, %2, %3, %4, %5, %6, %7, %8, %9, %10, %11}, {%12, %13, %14, %15}, %16, p, 1, 1, 1;\n}\n"
        : "+f"(d[0]), "+f"(d[1]), "+f"(d[2]), "+f"(d[3]), "+f"(d[4]), "+f"(d[5]), "+f"(d[6]), "+f"(d[7]), "+f"(d[8]), "+f"(d[9]), "+f"(d[10]), "+f"(d[11])
        : "r"(a0), "r"(a1), "r"(a2), "r"(a3), "l"(db));
}

constexpr int K1_STAGES = 5;
constexpr int K1_STAGE = 16384 + 24576;
constexpr int K1_OFF_BAR = K1_STAGES * K1_STAGE;
constexpr int K1_OFF_RS = K1_OFF_BAR + 128;
constexpr int K1_OFF_CS = K1_OFF_RS + 1024;
constexpr int K1_SMEM = K1_OFF_CS + 768 + 1024;

__device__ __forceinline__ unsigned int ld_acquire(const unsigned int* p) {
    unsigned int v;
    asm volatile("ld.acquire.gpu.global.u32 %0, [%1];" : "=r"(v) : "l"(p) : "memory");
    return v;
}
__device__ __forceinline__ bool spin_until(const unsigned int* p, unsigned int target) {
    for (int i = 0; i < 20000; i++) {
        if (ld_acquire(p) >= target) return true;
        __nanosleep(64);
    }
    return false;
}
template <int NR>
__device__ __forceinline__ float2 warp_row_stats(const __nv_bfloat16* __restrict__ x, int row, int lane) {
    const uint4* xp = reinterpret_cast<const uint4*>(x + (size_t)row * D_) + lane;
    uint4 v[NR][2];
#pragma unroll
    for (int r = 0; r < NR; r++) { v[r][0] = __ldg(xp + r * 64); v[r][1] = __ldg(xp + r * 64 + 32); }
    float mean[NR], var[NR];
#pragma unroll
    for (int r = 0; r < NR; r++) {
        const uint32_t w[8] = {v[r][0].x, v[r][0].y, v[r][0].z, v[r][0].w, v[r][1].x, v[r][1].y, v[r][1].z, v[r][1].w};
        float a0 = 0.f, a1 = 0.f;
#pragma unroll
        for (int j = 0; j < 8; j++) { a0 += bf_lo(w[j]); a1 += bf_hi(w[j]); }
        mean[r] = a0 + a1;
    }
#pragma unroll
    for (int o = 16; o > 0; o >>= 1)
#pragma unroll
        for (int r = 0; r < NR; r++) mean[r] += __shfl_xor_sync(0xffffffffu, mean[r], o);
#pragma unroll
    for (int r = 0; r < NR; r++) {
        mean[r] *= (1.f / D_);
        const uint32_t w[8] = {v[r][0].x, v[r][0].y, v[r][0].z, v[r][0].w, v[r][1].x, v[r][1].y, v[r][1].z, v[r][1].w};
        float a0 = 0.f, a1 = 0.f;
#pragma unroll
        for (int j = 0; j < 8; j++) {
            const float d0 = bf_lo(w[j]) - mean[r], d1 = bf_hi(w[j]) - mean[r];
            a0 = fmaf(d0, d0, a0); a1 = fmaf(d1, d1, a1);
        }
        var[r] = a0 + a1;
    }
#pragma unroll
    for (int o = 16; o > 0; o >>= 1)
#pragma unroll
        for (int r = 0; r < NR; r++) var[r] += __shfl_xor_sync(0xffffffffu, var[r], o);
    float mm = mean[0], vv = var[0];
#pragma unroll
    for (int r = 1; r < NR; r++)
        if (lane == r) { mm = mean[r]; vv = var[r]; }
    const float2 c = ln_consts(mm, vv * (1.f / D_));
    return make_float2(c.x, -c.y * c.x);
}
__device__ __forceinline__ void colsum32(const __nv_bfloat16* __restrict__ w, int k0, int col, float (&a)[8]) {
    const uint4* wp = reinterpret_cast<const uint4*>(w + (size_t)k0 * (3 * D_) + col);
#pragma unroll
    for (int h = 0; h < 2; h++) {
        uint4 v[16];
#pragma unroll
        for (int i = 0; i < 16; i++) v[i] = __ldg(wp + (size_t)(h * 16 + i) * (3 * D_ / 8));
#pragma unroll
        for (int i = 0; i < 16; i++) {
            a[0] += bf_lo(v[i].x); a[1] += bf_hi(v[i].x); a[2] += bf_lo(v[i].y); a[3] += bf_hi(v[i].y);
            a[4] += bf_lo(v[i].z); a[5] += bf_hi(v[i].z); a[6] += bf_lo(v[i].w); a[7] += bf_hi(v[i].w);
        }
    }
}

__global__ void __launch_bounds__(384, 1)
k1_qkv(const __grid_constant__ CUtensorMap tmX, const __grid_constant__ CUtensorMap tmW,
       const __nv_bfloat16* __restrict__ x, const __nv_bfloat16* __restrict__ w) {
    extern __shared__ uint8_t smem_raw[];
    const uint32_t sbase = (smem_u32(smem_raw) + 1023) & ~1023u;
    uint8_t* sptr = smem_raw + (sbase - smem_u32(smem_raw));
    const int tid = threadIdx.x, warp = tid >> 5, lane = tid & 31;
    const int nt = blockIdx.x & 7, mt = blockIdx.x >> 3;
    const uint32_t bar_full = sbase + K1_OFF_BAR, bar_empty = bar_full + 8 * K1_STAGES;
    float2* srs = reinterpret_cast<float2*>(sptr + K1_OFF_RS);
    float* scs = reinterpret_cast<float*>(sptr + K1_OFF_CS);
    TS(0, 0, tid == 0);
    if (warp == 8) {
        if (lane == 0) {
            for (int i = 0; i < K1_STAGES; i++) { mbar_init(bar_full + 8 * i, 1); mbar_init(bar_empty + 8 * i, 8); }
            fence_barrier_init();
        }
        __syncwarp();
        named_bar_arrive(1, 288);
        if (lane == 0) {
            for (int kt = 0; kt < 8; kt++) {
                const int s = kt % K1_STAGES;
                if (kt == K1_STAGES) pdl_launch();
                if (kt >= K1_STAGES) mbar_wait(bar_empty + 8 * s, ((kt / K1_STAGES) - 1) & 1);
                const uint32_t dst = sbase + s * K1_STAGE, bar = bar_full + 8 * s;
                mbar_expect_tx(bar, K1_STAGE);
                tma_load_2d(dst, &tmX, kt * 64, mt * 128, bar);
                tma_load_3d(dst + 16384, &tmW, 0, kt * 64, nt * 3, bar);
            }
        }
    } else if (warp == 9 || warp == 10) {
        const int r0 = mt * 128 + nt * 16 + (warp - 9) * 8;
        const float2 st = warp_row_stats<8>(x, r0, lane);
        if (lane < 8) g_rs[r0 + lane] = st;
        __threadfence();
        __syncwarp();
        if (lane == 0) atomicAdd(&g_cnt[mt], 1u);
        bool ok = true;
        if (lane == 0) ok = spin_until(&g_cnt[mt], 16u);
        ok = __shfl_sync(0xffffffffu, ok, 0);
        __syncwarp();
        const int lr = (warp - 9) * 64;
        if (ok) {
            srs[lr + lane] = __ldcg(&g_rs[mt * 128 + lr + lane]);
            srs[lr + 32 + lane] = __ldcg(&g_rs[mt * 128 + lr + 32 + lane]);
        } else {
            for (int r = 0; r < 64; r += 8) {
                const float2 t = warp_row_stats<8>(x, mt * 128 + lr + r, lane);
                if (lane < 8) srs[lr + r + lane] = t;
            }
        }
        __syncwarp();
        named_bar_arrive(2, 352);
    } else if (warp == 11) {
        float a[8];
#pragma unroll
        for (int j = 0; j < 8; j++) a[j] = 0.f;
        const int col = nt * 192 + lane * 8;
        if (lane < 24) {
            colsum32(w, mt * 32, col, a);
            float4* dst = reinterpret_cast<float4*>(g_csp + mt * (3 * D_) + col);
            dst[0] = make_float4(a[0], a[1], a[2], a[3]);
            dst[1] = make_float4(a[4], a[5], a[6], a[7]);
        }
        __threadfence();
        __syncwarp();
        if (lane == 0) atomicAdd(&g_cnt[16 + nt], 1u);
        bool ok = true;
        if (lane == 0) ok = spin_until(&g_cnt[16 + nt], 16u);
        ok = __shfl_sync(0xffffffffu, ok, 0);
        __syncwarp();
        if (lane < 24) {
#pragma unroll
            for (int j = 0; j < 8; j++) a[j] = 0.f;
            if (ok) {
#pragma unroll
                for (int g = 0; g < 16; g++) {
                    const float4 p0 = __ldcg(reinterpret_cast<const float4*>(g_csp + g * (3 * D_) + col));
                    const float4 p1 = __ldcg(reinterpret_cast<const float4*>(g_csp + g * (3 * D_) + col) + 1);
                    a[0] += p0.x; a[1] += p0.y; a[2] += p0.z; a[3] += p0.w; a[4] += p1.x; a[5] += p1.y; a[6] += p1.z; a[7] += p1.w;
                }
            } else {
#pragma unroll 1
                for (int g = 0; g < 16; g++) colsum32(w, g * 32, col, a);
            }
            *reinterpret_cast<float4*>(scs + lane * 8) = make_float4(a[0], a[1], a[2], a[3]);
            *reinterpret_cast<float4*>(scs + lane * 8 + 4) = make_float4(a[4], a[5], a[6], a[7]);
        }
        __syncwarp();
        named_bar_arrive(2, 352);
    } else {
        const int wg = warp >> 2;
        named_bar_sync(1, 288);
        float acc[96];
        for (int kt = 0; kt < 8; kt++) {
            const int s = kt % K1_STAGES;
            mbar_wait(bar_full + 8 * s, (kt / K1_STAGES) & 1);
            TS(0, 1, tid == 0 && kt == 0);
            const uint64_t da = make_desc(sbase + s * K1_STAGE + wg * 8192, 16, 1024, 1);
            const uint64_t db = make_desc(sbase + s * K1_STAGE + 16384, 8192, 1024, 1);
            wg_fence();
#pragma unroll
            for (int kk = 0; kk < 4; kk++) wgmma_ss_n192(acc, da + kk * 2, db + kk * 128, (kt | kk) != 0);
            wg_commit();
            if (kt > 0 && kt - 1 + K1_STAGES < 8) {
                wg_wait<1>();
                if (lane == 0) mbar_arrive(bar_empty + 8 * ((kt - 1) % K1_STAGES));
            }
        }
        named_bar_sync(2, 352);
        TS(0, 3, tid == 0);
        const int lr = warp * 16 + (lane >> 2);
        const float2 rs0 = srs[lr], rs1 = srs[lr + 8];
        const float* csf = scs + (lane & 3) * 2;
        wg_wait<0>();
        fence_regs(acc);
        TS(0, 2, tid == 0);
        const uint32_t stg = sbase + wg * 8192 + (lane >> 4) * 1024 + ((warp & 3) * 16 + (lane & 15)) * 16;
        float n0[12], n1[12];
#pragma unroll
        for (int hh = 0; hh < 12; hh++) {
            const float sc = (nt * 12 + hh < H_) ? QSCALE : 1.f;
            const float a0 = rs0.x * sc, b0 = rs0.y * sc, a1 = rs1.x * sc, b1 = rs1.y * sc;
            const float2 ca = *reinterpret_cast<const float2*>(csf + hh * 16), cb = *reinterpret_cast<const float2*>(csf + hh * 16 + 8);
            float a[8];
            a[0] = fmaf(a0, acc[8 * hh + 0], b0 * ca.x); a[1] = fmaf(a0, acc[8 * hh + 1], b0 * ca.y);
            a[2] = fmaf(a1, acc[8 * hh + 2], b1 * ca.x); a[3] = fmaf(a1, acc[8 * hh + 3], b1 * ca.y);
            a[4] = fmaf(a0, acc[8 * hh + 4], b0 * cb.x); a[5] = fmaf(a0, acc[8 * hh + 5], b0 * cb.y);
            a[6] = fmaf(a1, acc[8 * hh + 6], b1 * cb.x); a[7] = fmaf(a1, acc[8 * hh + 7], b1 * cb.y);
            stmatrix_x4(stg + (hh >> 2) * K1_STAGE + (hh & 3) * 2048, pack_bf16(a[0], a[1]), pack_bf16(a[2], a[3]),
                        pack_bf16(a[4], a[5]), pack_bf16(a[6], a[7]));
            n0[hh] = fmaf(a[0], a[0], fmaf(a[1], a[1], fmaf(a[4], a[4], a[5] * a[5])));
            n1[hh] = fmaf(a[2], a[2], fmaf(a[3], a[3], fmaf(a[6], a[6], a[7] * a[7])));
        }
        fence_proxy_async();
        named_bar_sync(3 + wg, 128);
        if (lane < 6) {
            const int c = (warp & 3) * 6 + lane;
            bulk_store(g_qkv + ((size_t)(nt * 24 + c) * S_ + mt * 128 + wg * 64) * 8,
                       sbase + (c >> 3) * K1_STAGE + wg * 8192 + (c & 7) * 1024, 1024);
            bulk_commit();
        }
#pragma unroll
        for (int hh = 0; hh < 12; hh++) { n0[hh] += __shfl_xor_sync(0xffffffffu, n0[hh], 1); n1[hh] += __shfl_xor_sync(0xffffffffu, n1[hh], 1); }
#pragma unroll
        for (int hh = 0; hh < 12; hh++) { n0[hh] += __shfl_xor_sync(0xffffffffu, n0[hh], 2); n1[hh] += __shfl_xor_sync(0xffffffffu, n1[hh], 2); }
        uint32_t mine = 0;
#pragma unroll
        for (int hh = 0; hh < 12; hh++) {
            const uint32_t mx = __reduce_max_sync(0xffffffffu, max(__float_as_uint(n0[hh]), __float_as_uint(n1[hh])));
            if (lane == hh) mine = mx;
        }
        if (lane < 12) g_nrm[(nt * 12 + lane) * 128 + mt * 8 + warp] = __uint_as_float(mine);
        if (lane < 6) bulk_wait_all();
        TS(0, 4, tid == 0);
    }
}

constexpr int AT_OFF_K = 0, AT_OFF_V = 65536, AT_OFF_ONE = 131072, AT_OFF_STG = 163840, AT_OFF_BAR = AT_OFF_STG + 16384;
constexpr int AT_SMEM = AT_OFF_BAR + 128 + 1024;
constexpr int AT_NCH = 4;
#define AT_NPOLY 20

__device__ __forceinline__ uint32_t exp2_pair_fma(float x0, float x1) {
    const float t0 = x0 + 65663.0f, t1 = x1 + 65663.0f;
    uint32_t y, m, l, p, r;
    asm("prmt.b32 %0, %1, %2, 0x5410;" : "=r"(y) : "r"(__float_as_uint(t0)), "r"(__float_as_uint(t1)));
    asm("lop3.b32 %0, %1, 0x007F007F, 0x3F803F80, 0xEA;" : "=r"(m) : "r"(y));
    asm("fma.rn.bf16x2 %0, %1, %2, %3;" : "=r"(l) : "r"(m), "r"(0x3EAD3EADu), "r"(0xBCB6BCB6u));
    asm("fma.rn.bf16x2 %0, %1, %2, %3;" : "=r"(p) : "r"(l), "r"(m), "r"(0x3F303F30u));
    asm("lop3.b32 %0, %1, %2, 0x007F007F, 0xE4;" : "=r"(r) : "r"(p), "r"(y));
    return r;
}

__device__ __forceinline__ void attn_store(const float (&o)[12], uint32_t stg, int m64, int head, int tid) {
    const int lane = tid & 31, w4 = (tid >> 5) & 3;
    const float l0 = __shfl_sync(0xffffffffu, o[8], lane & ~3), l1 = __shfl_sync(0xffffffffu, o[10], lane & ~3);
    const float i0 = __frcp_rn(l0), i1 = __frcp_rn(l1);
    stmatrix_x4(stg + (lane >> 4) * 1024 + (w4 * 16 + (lane & 15)) * 16, pack_bf16(o[0] * i0, o[1] * i0), pack_bf16(o[2] * i1, o[3] * i1),
                pack_bf16(o[4] * i0, o[5] * i0), pack_bf16(o[6] * i1, o[7] * i1));
    fence_proxy_async();
    named_bar_sync(1 + (tid >> 7), 128);
    if ((tid & 127) == 0) { bulk_store(g_o + (size_t)(m64 * H_ + head) * 1024, stg, 2048); bulk_commit(); }
}

__global__ void __launch_bounds__(512, 1)
k2_attn(const __nv_bfloat16* __restrict__ wo, const __nv_bfloat16* __restrict__ wg_,
        const __nv_bfloat16* __restrict__ wu, const __nv_bfloat16* __restrict__ wd) {
    extern __shared__ uint8_t smem_raw[];
    const uint32_t sbase = (smem_u32(smem_raw) + 1023) & ~1023u;
    uint8_t* sptr = smem_raw + (sbase - smem_u32(smem_raw));
    const int tid = threadIdx.x, warp = tid >> 5, lane = tid & 31, wg = warp >> 2;
    if (blockIdx.x >= 128) {
        const int sc = blockIdx.x - 128;
        if (tid == 0) {
            for (int i = 0; i < 8; i++) bulk_prefetch_l2(reinterpret_cast<const uint8_t*>(wo) + sc * 131072 + i * 16384, 16384);
            for (int i = 0; i < 28; i++) bulk_prefetch_l2(reinterpret_cast<const uint8_t*>(wd) + sc * 458752 + i * 16384, 16384);
        }
        bulk_prefetch_l2(((sc >> 1) ? wu : wg_) + (size_t)tid * F_ + (sc & 1) * 896, 1792);
        float* part = reinterpret_cast<float*>(sptr);
        if (tid < 448) {
            const int cc = tid % 112, rg = tid / 112;
            const __nv_bfloat16* w = ((sc >> 1) ? wu : wg_) + (size_t)rg * 128 * F_ + (sc & 1) * 896 + cc * 8;
            float a[8];
#pragma unroll
            for (int j = 0; j < 8; j++) a[j] = 0.f;
            for (int r = 0; r < 128; r += 16) {
                uint4 v[16];
#pragma unroll
                for (int i = 0; i < 16; i++) v[i] = __ldg(reinterpret_cast<const uint4*>(w + (size_t)(r + i) * F_));
#pragma unroll
                for (int i = 0; i < 16; i++) {
                    a[0] += bf_lo(v[i].x); a[1] += bf_hi(v[i].x); a[2] += bf_lo(v[i].y); a[3] += bf_hi(v[i].y);
                    a[4] += bf_lo(v[i].z); a[5] += bf_hi(v[i].z); a[6] += bf_lo(v[i].w); a[7] += bf_hi(v[i].w);
                }
            }
#pragma unroll
            for (int j = 0; j < 8; j++) part[rg * 896 + cc * 8 + j] = a[j];
        }
        __syncthreads();
        for (int c = tid; c < 896; c += 512)
            g_cs[(sc >> 1) * F_ + (sc & 1) * 896 + c] = (part[c] + part[896 + c]) + (part[1792 + c] + part[2688 + c]);
        return;
    }
    const int head = blockIdx.x >> 2, qblk = blockIdx.x & 3;
    const uint32_t bar = sbase + AT_OFF_BAR;
    TS(1, 0, tid == 0);
    if (tid == 0) {
        for (int i = 0; i < AT_NCH; i++) mbar_init(bar + 8 * i, 4);
        fence_barrier_init();
    }
#pragma unroll
    for (int i = 0; i < 4; i++)
        *reinterpret_cast<uint4*>(sptr + AT_OFF_ONE + (tid + i * 512) * 16) = make_uint4(0x00003F80u, 0u, 0u, 0u);
    fence_proxy_async();
    __syncthreads();
    TS(1, 1, tid == 0);
    pdl_wait();
    TS(1, 2, tid == 0);
    pdl_launch();
    if (blockIdx.x == 0 && tid < 32) g_cnt[tid] = 0;
    const __nv_bfloat16* kvsrc = g_qkv + (size_t)(((wg >> 1) + 1) * H_ * 2 + head * 2 + (wg & 1)) * S_ * 8;
    auto load_chunk = [&](int c) {
        if ((tid & 127) == 0) {
            mbar_expect_tx(bar + 8 * c, 32768 / AT_NCH);
            bulk_load(sbase + wg * 32768 + c * (32768 / AT_NCH), kvsrc + c * (S_ / AT_NCH) * 8, 32768 / AT_NCH, bar + 8 * c);
        }
    };
    load_chunk(0);
    load_chunk(1);
    const int q4 = lane & 3;
    const int rowb = qblk * 512 + wg * 128 + (warp & 3) * 16 + (lane >> 2);
    uint32_t qf[2][4];
    {
        const uint32_t* qp = reinterpret_cast<const uint32_t*>(g_qkv + ((size_t)(head * 2) * S_ + rowb) * 8) + q4;
#pragma unroll
        for (int it = 0; it < 2; it++) {
            qf[it][0] = qp[it * 256]; qf[it][1] = qp[it * 256 + 32]; qf[it][2] = qp[it * 256 + S_ * 4]; qf[it][3] = qp[it * 256 + S_ * 4 + 32];
        }
    }
    bool fast;
    {
        const float4* nq = reinterpret_cast<const float4*>(g_nrm + head * 128) + lane;
        const float4 a = nq[0], b = nq[H_ * 32], c = nq[2 * H_ * 32];
        const uint32_t qn = __reduce_max_sync(0xffffffffu, max(max(__float_as_uint(a.x), __float_as_uint(a.y)), max(__float_as_uint(a.z), __float_as_uint(a.w))));
        const uint32_t kn = __reduce_max_sync(0xffffffffu, max(max(__float_as_uint(b.x), __float_as_uint(b.y)), max(__float_as_uint(b.z), __float_as_uint(b.w))));
        const uint32_t vm = __reduce_max_sync(0xffffffffu, max(max(__float_as_uint(c.x), __float_as_uint(c.y)), max(__float_as_uint(c.z), __float_as_uint(c.w))));
        fast = (__uint_as_float(qn) * __uint_as_float(kn) <= 3800.f) && (__uint_as_float(vm) <= 1.0e30f);
    }
    const uint64_t dk0 = make_desc(sbase + AT_OFF_K, 32768, 128, 0);
    const uint64_t dv0 = make_desc(sbase + AT_OFF_V, 128, 32768, 0);

    if (fast) {
#pragma unroll 1
        for (int it = 0; it < 2; it++) {
            const uint32_t qa0 = it ? qf[1][0] : qf[0][0], qa1 = it ? qf[1][1] : qf[0][1];
            const uint32_t qa2 = it ? qf[1][2] : qf[0][2], qa3 = it ? qf[1][3] : qf[0][3];
            float o[12];
#pragma unroll
            for (int i = 0; i < 12; i++) o[i] = 0.f;
            TS(1, 3 + it, tid == 0);
            TC(1, 6, tid == 0 && it == 0);
#pragma unroll 1
            for (int c = 0; c < AT_NCH; c++) {
                if (it == 0) {
                    mbar_wait(bar + 8 * c, 0);
                    if (c + 2 < AT_NCH) load_chunk(c + 2);
                }
#pragma unroll 1
                for (int t = c * (16 / AT_NCH); t < (c + 1) * (16 / AT_NCH); t++) {
                    float s[64];
                    uint32_t p[32];
                    wg_fence();
                    wgmma_rs_n128_zero(s, qa0, qa1, qa2, qa3, dk0 + t * 128);
                    wg_commit();
                    wg_wait<0>();
                    fence_regs(s);
#pragma unroll
                    for (int kk = 0; kk < 8; kk++) {
#pragma unroll
                        for (int j = 4 * kk; j < 4 * kk + 4; j++) {
                            const bool poly = ((j + 1) * AT_NPOLY) / 32 != (j * AT_NPOLY) / 32;
                            p[j] = poly ? exp2_pair_fma(s[2 * j], s[2 * j + 1]) : pack_bf16(ex2(s[2 * j]), ex2(s[2 * j + 1]));
                        }
                        wg_fence();
                        wgmma_rs_n24_acc(o, p[4 * kk], p[4 * kk + 1], p[4 * kk + 2], p[4 * kk + 3], dv0 + t * 128 + kk * 16);
                    }
                    wg_commit();
                    wg_wait<0>();
                    fence_regs(o);
                }
            }
            attn_store(o, sbase + AT_OFF_STG + (wg * 2 + it) * 2048, qblk * 8 + wg * 2 + it, head, tid);
        }
    } else {
#pragma unroll 1
        for (int it = 0; it < 2; it++) {
            const uint32_t qa0 = it ? qf[1][0] : qf[0][0], qa1 = it ? qf[1][1] : qf[0][1];
            const uint32_t qa2 = it ? qf[1][2] : qf[0][2], qa3 = it ? qf[1][3] : qf[0][3];
            float o[12];
#pragma unroll
            for (int i = 0; i < 12; i++) o[i] = 0.f;
            float m0 = -INFINITY, m1 = -INFINITY;
#pragma unroll 1
            for (int t = 0; t < 16; t++) {
                float s[64];
                uint32_t p[32];
                if (it == 0 && (t % (16 / AT_NCH)) == 0) {
                    const int c = t / (16 / AT_NCH);
                    mbar_wait(bar + 8 * c, 0);
                    if (c + 2 < AT_NCH) load_chunk(c + 2);
                }
                wg_fence();
                wgmma_rs_n128_zero(s, qa0, qa1, qa2, qa3, dk0 + t * 128);
                wg_commit();
                wg_wait<0>();
                fence_regs(s);
                float t0 = m0, t1 = m1;
#pragma unroll
                for (int j = 0; j < 16; j++) {
                    t0 = fmaxf(t0, fmaxf(s[4 * j], s[4 * j + 1]));
                    t1 = fmaxf(t1, fmaxf(s[4 * j + 2], s[4 * j + 3]));
                }
                t0 = fmaxf(t0, __shfl_xor_sync(0xffffffffu, t0, 1)); t1 = fmaxf(t1, __shfl_xor_sync(0xffffffffu, t1, 1));
                t0 = fmaxf(t0, __shfl_xor_sync(0xffffffffu, t0, 2)); t1 = fmaxf(t1, __shfl_xor_sync(0xffffffffu, t1, 2));
                const float c0 = ex2(m0 - t0), c1 = ex2(m1 - t1);
                m0 = t0; m1 = t1;
#pragma unroll
                for (int i = 0; i < 3; i++) { o[4 * i] *= c0; o[4 * i + 1] *= c0; o[4 * i + 2] *= c1; o[4 * i + 3] *= c1; }
#pragma unroll
                for (int kk = 0; kk < 8; kk++) {
#pragma unroll
                    for (int j = 2 * kk; j < 2 * kk + 2; j++) {
                        p[2 * j] = pack_bf16(ex2(s[4 * j] - m0), ex2(s[4 * j + 1] - m0));
                        p[2 * j + 1] = pack_bf16(ex2(s[4 * j + 2] - m1), ex2(s[4 * j + 3] - m1));
                    }
                    wg_fence();
                    wgmma_rs_n24_acc(o, p[4 * kk], p[4 * kk + 1], p[4 * kk + 2], p[4 * kk + 3], dv0 + t * 128 + kk * 16);
                }
                wg_commit();
                wg_wait<0>();
                fence_regs(o);
            }
            attn_store(o, sbase + AT_OFF_STG + (wg * 2 + it) * 2048, qblk * 8 + wg * 2 + it, head, tid);
        }
    }
    if ((tid & 127) == 0) bulk_wait_all();
    TS(1, 5, tid == 0);
    TC(1, 7, tid == 0);
}

constexpr int K3_STAGE = 16384 + 8192;
constexpr int K3_OFF_STG = 8 * K3_STAGE;
constexpr int K3_OFF_BAR = K3_OFF_STG + 16384;
constexpr int K3_SMEM = K3_OFF_BAR + 64 + 1024;

__global__ void __launch_bounds__(288, 1)
k3_wo(const __grid_constant__ CUtensorMap tmW, const __grid_constant__ CUtensorMap tmOut, const __nv_bfloat16* __restrict__ x) {
    extern __shared__ uint8_t smem_raw[];
    const uint32_t sbase = (smem_u32(smem_raw) + 1023) & ~1023u;
    const int tid = threadIdx.x, warp = tid >> 5, lane = tid & 31;
    const int nt = blockIdx.x & 7, mt = blockIdx.x >> 3;
    const uint32_t bar_full = sbase + K3_OFF_BAR;
    TS(2, 0, tid == 0);
    if (warp == 8) {
        if (lane == 0) {
            for (int i = 0; i < 8; i++) mbar_init(bar_full + 8 * i, 1);
            fence_barrier_init();
            for (int kt = 0; kt < 8; kt++) {
                mbar_expect_tx(bar_full + 8 * kt, K3_STAGE);
                tma_load_3d(sbase + kt * K3_STAGE + 16384, &tmW, 0, kt * 64, nt, bar_full + 8 * kt);
            }
        }
        __syncwarp();
        named_bar_arrive(1, 288);
        if (lane == 0) {
            pdl_wait();
            pdl_launch();
            TS(2, 4, true);
            for (int kt = 0; kt < 8; kt++)
                for (int w = 0; w < 2; w++)
                    bulk_load(sbase + kt * K3_STAGE + w * 8192, g_o + (size_t)((mt * 2 + w) * H_ + kt * 4) * 1024, 8192, bar_full + 8 * kt);
        }
    } else {
        const int wg = warp >> 2;
        const int q4 = lane & 3;
        const int row0 = mt * 128 + warp * 16 + (lane >> 2);
        const size_t off = (size_t)row0 * D_ + nt * 64 + q4 * 2;
        uint32_t r0[8], r1[8];
#pragma unroll
        for (int i = 0; i < 8; i++) {
            r0[i] = *reinterpret_cast<const uint32_t*>(x + off + i * 8);
            r1[i] = *reinterpret_cast<const uint32_t*>(x + off + 8 * D_ + i * 8);
        }
        named_bar_sync(1, 288);
        float acc[32];
        for (int kt = 0; kt < 8; kt++) {
            mbar_wait(bar_full + 8 * kt, 0);
            TS(2, 1, tid == 0 && kt == 0);
            const uint64_t da = make_desc(sbase + kt * K3_STAGE + wg * 8192, 1024, 128, 0);
            const uint64_t db = make_desc(sbase + kt * K3_STAGE + 16384, 8192, 1024, 1);
            wg_fence();
#pragma unroll
            for (int kk = 0; kk < 4; kk++) wgmma_ss_n64(acc, da + kk * 128, db + kk * 128, (kt | kk) != 0);
            wg_commit();
        }
        wg_wait<0>();
        fence_regs(acc);
        TS(2, 2, tid == 0);
        float s0 = 0.f, s1 = 0.f;
#pragma unroll
        for (int i = 0; i < 8; i++) {
            r0[i] = pack_bf16(acc[4 * i] + bf_lo(r0[i]), acc[4 * i + 1] + bf_hi(r0[i]));
            r1[i] = pack_bf16(acc[4 * i + 2] + bf_lo(r1[i]), acc[4 * i + 3] + bf_hi(r1[i]));
            s0 += bf_lo(r0[i]) + bf_hi(r0[i]); s1 += bf_lo(r1[i]) + bf_hi(r1[i]);
        }
        {
            const uint32_t stg = sbase + K3_OFF_STG + wg * 8192;
            const int r = (warp & 3) * 16 + (lane & 15);
#pragma unroll
            for (int i = 0; i < 8; i += 2)
                stmatrix_x4(stg + r * 128 + (((i + (lane >> 4)) ^ (r & 7)) << 4), r0[i], r1[i], r0[i + 1], r1[i + 1]);
            fence_proxy_async();
            named_bar_sync(2 + wg, 128);
            if ((tid & 127) == 0) { tma_store_2d(&tmOut, stg, nt * 64, mt * 128 + wg * 64); bulk_commit(); }
        }
        s0 += __shfl_xor_sync(0xffffffffu, s0, 1); s1 += __shfl_xor_sync(0xffffffffu, s1, 1);
        s0 += __shfl_xor_sync(0xffffffffu, s0, 2); s1 += __shfl_xor_sync(0xffffffffu, s1, 2);
        const float m0 = s0 * (1.f / 64), m1 = s1 * (1.f / 64);
        float v0 = 0.f, v1 = 0.f;
#pragma unroll
        for (int i = 0; i < 8; i++) {
            float d;
            d = bf_lo(r0[i]) - m0; v0 = fmaf(d, d, v0); d = bf_hi(r0[i]) - m0; v0 = fmaf(d, d, v0);
            d = bf_lo(r1[i]) - m1; v1 = fmaf(d, d, v1); d = bf_hi(r1[i]) - m1; v1 = fmaf(d, d, v1);
        }
        v0 += __shfl_xor_sync(0xffffffffu, v0, 1); v1 += __shfl_xor_sync(0xffffffffu, v1, 1);
        v0 += __shfl_xor_sync(0xffffffffu, v0, 2); v1 += __shfl_xor_sync(0xffffffffu, v1, 2);
        if (q4 == 0) {
            g_stats[row0 * 8 + nt] = make_float2(m0, v0);
            g_stats[(row0 + 8) * 8 + nt] = make_float2(m1, v1);
        }
        if ((tid & 127) == 0) bulk_wait_all();
        TS(2, 3, tid == 0);
    }
}

constexpr int K5_KT = F_ / 64;
constexpr int K5_STAGES = 6;
constexpr int K5_STAGE = 8192 + 16384;
constexpr int K5_OFF_RED = K5_STAGES * K5_STAGE;
constexpr int K5_OFF_BAR = K5_OFF_RED + 32768;
constexpr int K5_SMEM = K5_OFF_BAR + 128 + 1024;

__global__ void __launch_bounds__(288, 1)
k5_down(const __grid_constant__ CUtensorMap tmA, const __grid_constant__ CUtensorMap tmW, const __grid_constant__ CUtensorMap tmOut) {
    extern __shared__ uint8_t smem_raw[];
    const uint32_t sbase = (smem_u32(smem_raw) + 1023) & ~1023u;
    const int tid = threadIdx.x, warp = tid >> 5, lane = tid & 31;
    const int nt = blockIdx.x & 3, mt = blockIdx.x >> 2;
    const uint32_t bar_full = sbase + K5_OFF_BAR, bar_empty = bar_full + 8 * K5_STAGES;
    TS(4, 0, tid == 0);
    if (warp == 8) {
        if (lane == 0) {
            for (int i = 0; i < K5_STAGES; i++) { mbar_init(bar_full + 8 * i, 1); mbar_init(bar_empty + 8 * i, 4); }
            fence_barrier_init();
            for (int kt = 0; kt < K5_STAGES; kt++) {
                mbar_expect_tx(bar_full + 8 * kt, K5_STAGE);
                tma_load_3d(sbase + kt * K5_STAGE + 8192, &tmW, 0, kt * 64, nt * 2, bar_full + 8 * kt);
            }
        }
        __syncwarp();
        named_bar_arrive(1, 288);
        if (lane == 0) {
            pdl_wait();
            TS(4, 4, true);
            for (int kt = 0; kt < K5_KT; kt++) {
                const int s = kt % K5_STAGES;
                if (kt >= K5_STAGES) {
                    mbar_wait(bar_empty + 8 * s, ((kt / K5_STAGES) - 1) & 1);
                    mbar_expect_tx(bar_full + 8 * s, K5_STAGE);
                }
                tma_load_2d(sbase + s * K5_STAGE, &tmA, kt * 64, mt * 64, bar_full + 8 * s);
                if (kt >= K5_STAGES) tma_load_3d(sbase + s * K5_STAGE + 8192, &tmW, 0, kt * 64, nt * 2, bar_full + 8 * s);
            }
        }
    } else {
        const int wg = warp >> 2, t128 = tid & 127;
        const int row0 = mt * 64 + (warp & 3) * 16 + (lane >> 2);
        const __nv_bfloat16* res = g_h + (size_t)row0 * D_ + nt * 128 + wg * 64 + (lane & 3) * 2;
        uint32_t r0[8], r1[8];
#pragma unroll
        for (int i = 0; i < 8; i++) {
            r0[i] = *reinterpret_cast<const uint32_t*>(res + i * 8);
            r1[i] = *reinterpret_cast<const uint32_t*>(res + 8 * D_ + i * 8);
        }
        named_bar_sync(1, 288);
        float acc[64];
        for (int i = 0; i < K5_KT / 2; i++) {
            const int kt = 2 * i + wg, s = kt % K5_STAGES;
            mbar_wait(bar_full + 8 * s, (kt / K5_STAGES) & 1);
            TS(4, 1, tid == 0 && kt == 0);
            const uint64_t da = make_desc(sbase + s * K5_STAGE, 16, 1024, 1);
            const uint64_t db = make_desc(sbase + s * K5_STAGE + 8192, 8192, 1024, 1);
            wg_fence();
#pragma unroll
            for (int kk = 0; kk < 4; kk++) wgmma_ss_n128(acc, da + kk * 2, db + kk * 128, (i | kk) != 0);
            wg_commit();
            if (i > 0) {
                wg_wait<1>();
                if (lane == 0) mbar_arrive(bar_empty + 8 * ((kt - 2) % K5_STAGES));
            }
        }
        wg_wait<0>();
        fence_regs(acc);
        TS(4, 2, tid == 0);
        const uint32_t red = sbase + K5_OFF_RED;
#pragma unroll
        for (int i = 0; i < 8; i++) {
            const float a0 = wg ? acc[4 * i] : acc[32 + 4 * i], a1 = wg ? acc[4 * i + 1] : acc[32 + 4 * i + 1];
            const float a2 = wg ? acc[4 * i + 2] : acc[32 + 4 * i + 2], a3 = wg ? acc[4 * i + 3] : acc[32 + 4 * i + 3];
            sts128(red + (wg ^ 1) * 16384 + i * 2048 + t128 * 16, __float_as_uint(a0), __float_as_uint(a1), __float_as_uint(a2), __float_as_uint(a3));
        }
        float mine[32];
#pragma unroll
        for (int i = 0; i < 32; i++) mine[i] = wg ? acc[32 + i] : acc[i];
        named_bar_sync(2, 256);
#pragma unroll
        for (int i = 0; i < 8; i++) {
            const uint4 pv = lds128(red + wg * 16384 + i * 2048 + t128 * 16);
            r0[i] = pack_bf16(mine[4 * i] + __uint_as_float(pv.x) + bf_lo(r0[i]), mine[4 * i + 1] + __uint_as_float(pv.y) + bf_hi(r0[i]));
            r1[i] = pack_bf16(mine[4 * i + 2] + __uint_as_float(pv.z) + bf_lo(r1[i]), mine[4 * i + 3] + __uint_as_float(pv.w) + bf_hi(r1[i]));
        }
        const uint32_t stg = sbase + wg * K5_STAGE;
        const int r = (warp & 3) * 16 + (lane & 15);
#pragma unroll
        for (int i = 0; i < 8; i += 2)
            stmatrix_x4(stg + r * 128 + (((i + (lane >> 4)) ^ (r & 7)) << 4), r0[i], r1[i], r0[i + 1], r1[i + 1]);
        fence_proxy_async();
        named_bar_sync(3 + wg, 128);
        if (t128 == 0) { tma_store_2d(&tmOut, stg, nt * 128 + wg * 64, mt * 64); bulk_commit(); bulk_wait_all(); }
        TS(4, 3, tid == 0);
    }
}

constexpr int K4_STAGES = 6;
constexpr int K4_BSTAGE = 12288;
constexpr int K4_OFF_B = 8 * 16384;
constexpr int K4_OFF_STG = K4_OFF_B + K4_STAGES * K4_BSTAGE;
constexpr int K4_OFF_BAR = K4_OFF_STG + 24576;
constexpr int K4_OFF_CS = K4_OFF_BAR + 256;
constexpr int K4_SMEM = K4_OFF_CS + 1792 + 1024;

__device__ __forceinline__ float2 ln_from_stats(int row) {
    const float4* p = reinterpret_cast<const float4*>(g_stats + row * 8);
    float4 v[4];
#pragma unroll
    for (int i = 0; i < 4; i++) v[i] = __ldcg(p + i);
    float mean = 0.f;
#pragma unroll
    for (int i = 0; i < 4; i++) mean += v[i].x + v[i].z;
    mean *= 0.125f;
    float m2 = 0.f;
#pragma unroll
    for (int i = 0; i < 4; i++) {
        const float d0 = v[i].x - mean, d1 = v[i].z - mean;
        m2 += v[i].y + v[i].w + 64.f * (d0 * d0 + d1 * d1);
    }
    return ln_consts(mean, m2 * (1.f / D_));
}
struct RowConst { float nm, k0, k1, h; };
__device__ __forceinline__ RowConst row_const(int row) {
    const float2 st = ln_from_stats(row);
    RowConst c;
    c.nm = -st.y;
    c.k0 = 0.7978845608028654f * st.x;
    c.k1 = 0.044715f * 0.7978845608028654f * st.x * st.x * st.x;
    c.h = 0.5f * st.x * st.x;
    return c;
}
__device__ __forceinline__ float geglu(const RowConst& c, float accg, float csg, float accu, float csu) {
    const float g = fmaf(c.nm, csg, accg), u = fmaf(c.nm, csu, accu);
    const float z = g * fmaf(g * g, c.k1, c.k0);
    const float hg = g * c.h;
    return fmaf(hg, tanh_fast(z), hg) * u;
}
template <int NC, int I0, int I1>
__device__ __forceinline__ void k4_epi(const float (&acc)[NC * 8], const RowConst& c0, const RowConst& c1, const float* csg,
                                       uint32_t stg, int sr, int hi) {
#pragma unroll
    for (int i2 = I0; i2 < I1; i2 += 2) {
        uint32_t w[4];
#pragma unroll
        for (int h = 0; h < 2; h++) {
            const int i = i2 + h;
            const float2 cg = *reinterpret_cast<const float2*>(csg + i * 8);
            const float2 cu = *reinterpret_cast<const float2*>(csg + 224 + i * 8);
            const float* ag = acc + 4 * i;
            const float* au = acc + 4 * NC + 4 * i;
            w[2 * h] = pack_bf16(geglu(c0, ag[0], cg.x, au[0], cu.x), geglu(c0, ag[1], cg.y, au[1], cu.y));
            w[2 * h + 1] = pack_bf16(geglu(c1, ag[2], cg.x, au[2], cu.x), geglu(c1, ag[3], cg.y, au[3], cu.y));
        }
        const uint32_t addr = NC == 8 ? stg + sr * 128 + ((i2 ^ (hi ^ (sr & 7))) << 4)
                                      : stg + sr * 64 + (i2 >> 2) * 4096 + (((i2 & 3) ^ (hi ^ ((sr >> 1) & 3))) << 4);
        stmatrix_x4(addr, w[0], w[1], w[2], w[3]);
    }
}
template <int W>
__device__ __forceinline__ void k4_store(const CUtensorMap* tm3, const CUtensorMap* tm2, uint32_t stg, int wg, int tid, int row, int sub) {
    fence_proxy_async();
    named_bar_sync(2 + wg, 128);
    if ((tid & 127) == 0) {
        if (W == 3) tma_store_3d(tm3, stg, 0, row, sub); else tma_store_2d(tm2, stg, sub * 32, row);
        bulk_commit();
    }
}
__device__ __forceinline__ void k4_stg_free(int wg, int tid) {
    if ((tid & 127) == 0) bulk_wait_read();
    named_bar_sync(2 + wg, 128);
}

constexpr int K4_W0 = 2, K4_W1 = 3, K4_W2 = 2;
__device__ __forceinline__ void k4_mma(float (&acc)[64], uint64_t da, uint64_t db128, uint64_t db64, int kk, int sd) {
    (void)db64; wgmma_ss_n128(acc, da, db128 + kk * 128, sd);
}
__device__ __forceinline__ void k4_mma(float (&acc)[96], uint64_t da, uint64_t db128, uint64_t db64, int kk, int sd) {
    (void)db128; wgmma_ss_n192(acc, da, db64 + kk * 64, sd);
}
template <int NP, int C>
__device__ __forceinline__ void k4_chunk(int jj, const float (&prev)[NP * 8], const RowConst& c0, const RowConst& c1, const float* csg,
                                         uint32_t stg, int sr, int hi) {
    if constexpr (C < NP / 2) {
        if (jj == 1 + C * 13 / (NP / 2)) k4_epi<NP, 2 * C, 2 * C + 2>(prev, c0, c1, csg, stg, sr, hi);
        k4_chunk<NP, C + 1>(jj, prev, c0, c1, csg, stg, sr, hi);
    }
}

__global__ void __launch_bounds__(384, 1)
k4_gateup(const __grid_constant__ CUtensorMap tmA, const __grid_constant__ CUtensorMap tmG3, const __grid_constant__ CUtensorMap tmU3,
          const __grid_constant__ CUtensorMap tmG2, const __grid_constant__ CUtensorMap tmU2,
          const __grid_constant__ CUtensorMap tmO3, const __grid_constant__ CUtensorMap tmO2) {
    extern __shared__ uint8_t smem_raw[];
    const uint32_t sbase = (smem_u32(smem_raw) + 1023) & ~1023u;
    const int tid = threadIdx.x, warp = tid >> 5, lane = tid & 31;
    const int nt = blockIdx.x & 7, mt = blockIdx.x >> 3;
    const uint32_t bar_full = sbase + K4_OFF_BAR, bar_empty = bar_full + 8 * K4_STAGES, bar_a = bar_empty + 8 * K4_STAGES;
    float* scs = reinterpret_cast<float*>(smem_raw + (sbase - smem_u32(smem_raw)) + K4_OFF_CS);
    TS(3, 0, tid == 0);
    if (tid == 256) {
        for (int i = 0; i < K4_STAGES; i++) { mbar_init(bar_full + 8 * i, 2); mbar_init(bar_empty + 8 * i, 8); }
        for (int i = 0; i < 8; i++) mbar_init(bar_a + 8 * i, 1);
        fence_barrier_init();
    }
    __syncthreads();
    if (warp >= 8) {
        asm volatile("setmaxnreg.dec.sync.aligned.u32 40;");
        if (warp < 10 && lane == 0) {
            const int up = warp - 8;
            const CUtensorMap* t3 = up ? &tmU3 : &tmG3;
            const CUtensorMap* t2 = up ? &tmU2 : &tmG2;
            int s = 0, ph = 1;
            for (int j = 0; j < 48; j++) {
                const int ks = j & 15, pass = j >> 4;
                const int w = pass == 0 ? K4_W0 : (pass == 1 ? K4_W1 : K4_W2);
                const int sub = pass == 0 ? 0 : (pass == 1 ? K4_W0 : K4_W0 + K4_W1);
                if (j >= K4_STAGES) mbar_wait(bar_empty + 8 * s, ph);
                const uint32_t dst = sbase + K4_OFF_B + s * K4_BSTAGE, bar = bar_full + 8 * s;
                if (w == 3) {
                    mbar_expect_tx(bar, 6144);
                    tma_load_3d(dst + up * 6144, t3, 0, ks * 32, nt * 7 + sub, bar);
                } else {
                    mbar_expect_tx(bar, 4096);
                    tma_load_2d(dst + up * 4096, t2, (nt * 7 + sub) * 32, ks * 32, bar);
                }
                if (++s == K4_STAGES) { s = 0; ph ^= 1; }
            }
        } else if (warp == 10 && lane == 0) {
            pdl_wait();
            pdl_launch();
            TS(3, 6, true);
            for (int i = 0; i < 8; i++) {
                mbar_expect_tx(bar_a + 8 * i, 16384);
                tma_load_2d(sbase + i * 16384, &tmA, i * 64, mt * 128, bar_a + 8 * i);
            }
        }
    } else {
        asm volatile("setmaxnreg.inc.sync.aligned.u32 232;");
        if (tid < 224) { scs[tid] = g_cs[nt * 224 + tid]; scs[224 + tid] = g_cs[F_ + nt * 224 + tid]; }
        named_bar_sync(1, 256);
        const int wg = warp >> 2;
        const int row0 = mt * 128 + warp * 16 + (lane >> 2);
        const float* csg = scs + (lane & 3) * 2;
        const uint32_t stg = sbase + K4_OFF_STG + wg * 12288;
        const int sr = (warp & 3) * 16 + (lane & 15), hi = lane >> 4;
        const uint64_t da0 = make_desc(sbase + wg * 8192, 16, 1024, 1);
        const uint64_t db64 = make_desc(sbase + K4_OFF_B, 2048, 512, 2);
        const uint64_t db128 = make_desc(sbase + K4_OFF_B, 4096, 1024, 1);
        const int orow = mt * 128 + wg * 64;
        float acc1[K4_W0 * 32], acc2[K4_W1 * 32], acc3[K4_W2 * 32];
        RowConst c0, c1;
#pragma unroll 2
        for (int j = 0; j < 16; j++) {
            const int s = j % K4_STAGES;
            if ((j & 1) == 0) mbar_wait(bar_a + 8 * (j >> 1), 0);
            mbar_wait(bar_full + 8 * s, (j / K4_STAGES) & 1);
            TS(3, 1, tid == 0 && j == 0);
            wg_fence();
#pragma unroll
            for (int kk = 0; kk < 2; kk++)
                k4_mma(acc1, da0 + (j >> 1) * 1024 + (j & 1) * 4 + kk * 2, db128 + s * (K4_BSTAGE >> 4), db64 + s * (K4_BSTAGE >> 4), kk, (j | kk) != 0);
            wg_commit();
            if (j > 0) { wg_wait<1>(); if (lane == 0) mbar_arrive(bar_empty + 8 * ((j - 1) % K4_STAGES)); }
            if (j == 5) { c0 = row_const(row0); c1 = row_const(row0 + 8); }
        }
        TS(3, 2, tid == 0);
#pragma unroll
        for (int jj = 0; jj < 16; jj++) {
            const int j = jj + 16, s = j % K4_STAGES;
            mbar_wait(bar_full + 8 * s, (j / K4_STAGES) & 1);
            wg_fence();
#pragma unroll
            for (int kk = 0; kk < 2; kk++)
                k4_mma(acc2, da0 + (jj >> 1) * 1024 + (jj & 1) * 4 + kk * 2, db128 + s * (K4_BSTAGE >> 4), db64 + s * (K4_BSTAGE >> 4), kk, (jj | kk) != 0);
            wg_commit();
            wg_wait<1>();
            if (lane == 0) mbar_arrive(bar_empty + 8 * ((j - 1) % K4_STAGES));
            if (jj == 0) fence_regs(acc1);
            k4_chunk<K4_W0 * 4, 0>(jj, acc1, c0, c1, csg, stg, sr, hi);
            if (jj == 13) k4_store<K4_W0>(&tmO3, &tmO2, stg, wg, tid, orow, nt * 7);
        }
        TS(3, 3, tid == 0);
#pragma unroll
        for (int jj = 0; jj < 16; jj++) {
            const int j = jj + 32, s = j % K4_STAGES;
            mbar_wait(bar_full + 8 * s, (j / K4_STAGES) & 1);
            wg_fence();
#pragma unroll
            for (int kk = 0; kk < 2; kk++)
                k4_mma(acc3, da0 + (jj >> 1) * 1024 + (jj & 1) * 4 + kk * 2, db128 + s * (K4_BSTAGE >> 4), db64 + s * (K4_BSTAGE >> 4), kk, (jj | kk) != 0);
            wg_commit();
            wg_wait<1>();
            if (j - 1 + K4_STAGES < 48 && lane == 0) mbar_arrive(bar_empty + 8 * ((j - 1) % K4_STAGES));
            if (jj == 0) { fence_regs(acc2); k4_stg_free(wg, tid); }
            k4_chunk<K4_W1 * 4, 0>(jj, acc2, c0, c1, csg + K4_W0 * 32, stg, sr, hi);
            if (jj == 13) k4_store<K4_W1>(&tmO3, &tmO2, stg, wg, tid, orow, nt * 7 + K4_W0);
        }
        wg_wait<0>();
        fence_regs(acc3);
        TS(3, 4, tid == 0);
        k4_epi<8, 0, 8>(acc3, c0, c1, csg + (K4_W0 + K4_W1) * 32, sbase + wg * 8192, sr, hi);
        k4_store<2>(&tmO3, &tmO2, sbase + wg * 8192, wg, tid, orow, nt * 7 + K4_W0 + K4_W1);
        if ((tid & 127) == 0) bulk_wait_all();
        TS(3, 5, tid == 0);
    }
}

typedef CUresult (*EncodeFn)(CUtensorMap*, CUtensorMapDataType, cuuint32_t, void*, const cuuint64_t*, const cuuint64_t*,
                             const cuuint32_t*, const cuuint32_t*, CUtensorMapInterleave, CUtensorMapSwizzle,
                             CUtensorMapL2promotion, CUtensorMapFloatOOBfill);

struct Maps { CUtensorMap hst, outst, act3, act1, x, wqkv, wo, h, wg3, wu3, wg1, wu1, act, wd; };

void make_a_map(EncodeFn enc, CUtensorMap* m, const void* p, int rows, int cols, int brows = 128) {
    cuuint64_t dims[2] = {(cuuint64_t)cols, (cuuint64_t)rows};
    cuuint64_t strides[1] = {(cuuint64_t)cols * 2};
    cuuint32_t box[2] = {64, (cuuint32_t)brows}, es[2] = {1, 1};
    enc(m, CU_TENSOR_MAP_DATA_TYPE_BFLOAT16, 2, const_cast<void*>(p), dims, strides, box, es, CU_TENSOR_MAP_INTERLEAVE_NONE,
        CU_TENSOR_MAP_SWIZZLE_128B, CU_TENSOR_MAP_L2_PROMOTION_L2_128B, CU_TENSOR_MAP_FLOAT_OOB_FILL_NONE);
}
void make_b_map(EncodeFn enc, CUtensorMap* m, const void* p, int K, int N, int sub, int nsub, int krows = 64) {
    cuuint64_t dims[3] = {(cuuint64_t)sub, (cuuint64_t)K, (cuuint64_t)(N / sub)};
    cuuint64_t strides[2] = {(cuuint64_t)N * 2, (cuuint64_t)sub * 2};
    cuuint32_t box[3] = {(cuuint32_t)sub, (cuuint32_t)krows, (cuuint32_t)nsub}, es[3] = {1, 1, 1};
    enc(m, CU_TENSOR_MAP_DATA_TYPE_BFLOAT16, 3, const_cast<void*>(p), dims, strides, box, es, CU_TENSOR_MAP_INTERLEAVE_NONE,
        sub == 64 ? CU_TENSOR_MAP_SWIZZLE_128B : CU_TENSOR_MAP_SWIZZLE_64B, CU_TENSOR_MAP_L2_PROMOTION_L2_128B,
        CU_TENSOR_MAP_FLOAT_OOB_FILL_NONE);
}

void make_st_map(EncodeFn enc, CUtensorMap* m, const void* p, int rows, int cols, int brows, int bcols, CUtensorMapSwizzle sw) {
    cuuint64_t dims[2] = {(cuuint64_t)cols, (cuuint64_t)rows};
    cuuint64_t strides[1] = {(cuuint64_t)cols * 2};
    cuuint32_t box[2] = {(cuuint32_t)bcols, (cuuint32_t)brows}, es[2] = {1, 1};
    enc(m, CU_TENSOR_MAP_DATA_TYPE_BFLOAT16, 2, const_cast<void*>(p), dims, strides, box, es, CU_TENSOR_MAP_INTERLEAVE_NONE,
        sw, CU_TENSOR_MAP_L2_PROMOTION_NONE, CU_TENSOR_MAP_FLOAT_OOB_FILL_NONE);
}

template <typename... KArgs, typename... Args>
void launch(void (*kern)(KArgs...), int grid, int block, int smem, bool pdl, Args... args) {
    cudaLaunchConfig_t cfg = {};
    cfg.gridDim = dim3(grid); cfg.blockDim = dim3(block); cfg.dynamicSmemBytes = smem; cfg.stream = cudaStreamPerThread;
    cudaLaunchAttribute at[1];
    int n = 0;
    if (pdl) { at[n].id = cudaLaunchAttributeProgrammaticStreamSerialization; at[n].val.programmaticStreamSerializationAllowed = 1; n++; }
    cfg.attrs = at; cfg.numAttrs = n;
    cudaLaunchKernelEx(&cfg, kern, KArgs(args)...);
}
template <typename K> void set_smem(K kern, int bytes) {
    cudaFuncSetAttribute(kern, cudaFuncAttributeMaxDynamicSharedMemorySize, bytes);
    cudaFuncSetAttribute(kern, cudaFuncAttributePreferredSharedMemoryCarveout, 100);
}

}

extern "C" void kernel_launch(void* const* d_in, const int* in_sizes, int n_in, void* d_out, int out_size) {
    (void)in_sizes; (void)n_in; (void)out_size;
    const __nv_bfloat16* x = (const __nv_bfloat16*)d_in[0];
    const __nv_bfloat16* wqkv = (const __nv_bfloat16*)d_in[1];
    const __nv_bfloat16* wo = (const __nv_bfloat16*)d_in[2];
    const __nv_bfloat16* wg = (const __nv_bfloat16*)d_in[4];
    const __nv_bfloat16* wu = (const __nv_bfloat16*)d_in[5];
    const __nv_bfloat16* wd = (const __nv_bfloat16*)d_in[6];
    __nv_bfloat16* out = (__nv_bfloat16*)d_out;

    static Maps maps;
    static const void* cached[7] = {nullptr, nullptr, nullptr, nullptr, nullptr, nullptr, nullptr};
    const void* cur[7] = {x, wqkv, wo, wg, wu, wd, out};
    bool same = true;
    for (int i = 0; i < 7; i++) same = same && cached[i] == cur[i];
    if (!same) {
        void* fn = nullptr;
        cudaDriverEntryPointQueryResult qr;
        cudaGetDriverEntryPoint("cuTensorMapEncodeTiled", &fn, cudaEnableDefault, &qr);
        EncodeFn enc = (EncodeFn)fn;
        void *phv, *pa;
        cudaGetSymbolAddress(&phv, g_h);
        cudaGetSymbolAddress(&pa, g_act);
        make_a_map(enc, &maps.x, x, S_, D_);
        make_b_map(enc, &maps.wqkv, wqkv, D_, 3 * D_, 64, 3);
        make_b_map(enc, &maps.wo, wo, D_, D_, 64, 1);
        make_a_map(enc, &maps.h, phv, S_, D_);
        make_b_map(enc, &maps.wg3, wg, D_, F_, 32, 3, 32);
        make_b_map(enc, &maps.wu3, wu, D_, F_, 32, 3, 32);
        make_a_map(enc, &maps.wg1, wg, D_, F_, 32);
        make_a_map(enc, &maps.wu1, wu, D_, F_, 32);
        make_a_map(enc, &maps.act, pa, S_, F_, 64);
        make_b_map(enc, &maps.wd, wd, F_, D_, 64, 2);
        make_st_map(enc, &maps.hst, phv, S_, D_, 64, 64, CU_TENSOR_MAP_SWIZZLE_128B);
        make_st_map(enc, &maps.outst, out, S_, D_, 64, 64, CU_TENSOR_MAP_SWIZZLE_128B);
        make_b_map(enc, &maps.act3, pa, S_, F_, 32, 3, 64);
        make_st_map(enc, &maps.act1, pa, S_, F_, 64, 64, CU_TENSOR_MAP_SWIZZLE_128B);
        set_smem(k1_qkv, K1_SMEM);
        set_smem(k2_attn, AT_SMEM);
        set_smem(k4_gateup, K4_SMEM);
        set_smem(k3_wo, K3_SMEM);
        set_smem(k5_down, K5_SMEM);
        for (int i = 0; i < 7; i++) cached[i] = cur[i];
    }
    const bool pdl = true;
    launch(k1_qkv, 128, 384, K1_SMEM, false, maps.x, maps.wqkv, x, wqkv);
    launch(k2_attn, 132, 512, AT_SMEM, pdl, wo, wg, wu, wd);
    launch(k3_wo, 128, 288, K3_SMEM, pdl, maps.wo, maps.hst, x);
    launch(k4_gateup, 128, 384, K4_SMEM, pdl, maps.h, maps.wg3, maps.wu3, maps.wg1, maps.wu1, maps.act3, maps.act1);
    launch(k5_down, 128, 288, K5_SMEM, pdl, maps.act, maps.wd, maps.outst);
}
```
